```python
import torch

def _softmax(x, axis=-1):
    return torch.softmax(x, dim=axis)
def _gelu(x):
    return torch.nn.functional.gelu(x, approximate="tanh")
def _silu(x):
    return torch.nn.functional.silu(x)
def _sigmoid(x):
    return torch.sigmoid(x)
def _layernorm(x, axis=-1, eps=1e-5):
    m = x.mean(dim=axis, keepdim=True)
    v = x.var(dim=axis, keepdim=True, unbiased=False)
    return (x - m) / torch.sqrt(v + eps)
def _scatter_add(tgt, idx, src, axis=0):
    return tgt.clone().index_add_(axis, idx, src)
def _segment_sum(src, seg, n):
    out = torch.zeros((n,) + src.shape[1:], dtype=src.dtype)
    return out.index_add_(0, seg, src)
def _pad(x, pw):
    flat = tuple(v for pair in reversed(pw) for v in pair)
    return torch.nn.functional.pad(x, flat)

kernel_name = 'standalone__rezero__sampling'

def setup_inputs():

    _w = (lambda a: (lambda t: t.to(torch.bfloat16) if t.is_floating_point() else t)(torch.as_tensor(a)))
    B, S, D = 1024, 32, 448
    return {
        "x": _w((lambda *s: torch.randn(*s, dtype=torch.bfloat16) * 0.05)(B, S, D)),
        "fx": _w((lambda *s: torch.randn(*s, dtype=torch.bfloat16) * 0.8)(B, S, D)),
        "alpha": _w((lambda *s: torch.randn(*s, dtype=torch.bfloat16) * 0.8)(1) * 0.1),
    }

def reference(x, fx, alpha):
    return x + alpha * fx
```

```cpp
#include <cuda_runtime.h>
#include <cuda_bf16.h>
#include <stdint.h>


__device__ __forceinline__ uint32_t rezero2(uint32_t x, uint32_t f, uint32_t a) {
    uint32_t t, o;
    asm("mul.rn.bf16x2 %0, %1, %2;" : "=r"(t) : "r"(a), "r"(f));
    asm("add.rn.bf16x2 %0, %1, %2;" : "=r"(o) : "r"(x), "r"(t));
    return o;
}

__global__ void __launch_bounds__(256) standalone__rezero__sampling_kernel(
    const uint4* __restrict__ x, const uint4* __restrict__ fx,
    const unsigned short* __restrict__ alpha, uint4* __restrict__ out, int n16) {
    int i = blockIdx.x * 256 + threadIdx.x;
    if (i >= n16) return;
    uint32_t a = (uint32_t)__ldg(alpha);
    a |= a << 16;
    uint4 xv = __ldg(x + i);
    uint4 fv = __ldg(fx + i);
    uint4 o;
    o.x = rezero2(xv.x, fv.x, a);
    o.y = rezero2(xv.y, fv.y, a);
    o.z = rezero2(xv.z, fv.z, a);
    o.w = rezero2(xv.w, fv.w, a);
    out[i] = o;
}

extern "C" void kernel_launch(void* const* d_in, const int* in_sizes, int n_in,
                              void* d_out, int out_size) {
    const uint4* x = (const uint4*)d_in[0];
    const uint4* fx = (const uint4*)d_in[1];
    const unsigned short* alpha = (const unsigned short*)d_in[2];
    int n16 = out_size / 8;
    standalone__rezero__sampling_kernel<<<(n16 + 255) / 256, 256>>>(x, fx, alpha, (uint4*)d_out, n16);
}
```

```cpp
#include <cuda_runtime.h>
#include <cuda_bf16.h>
#include <stdint.h>
#include <stdio.h>
__device__ __forceinline__ uint32_t rezero2(uint32_t x, uint32_t f, uint32_t a) {
    uint32_t t, o;
    asm("mul.rn.bf16x2 %0, %1, %2;" : "=r"(t) : "r"(a), "r"(f));
    asm("add.rn.bf16x2 %0, %1, %2;" : "=r"(o) : "r"(x), "r"(t));
    return o;
}
__global__ void k(const uint4* x, const uint4* fx, const unsigned short* alpha, uint4* out, int n16) {
    int i = blockIdx.x * 256 + threadIdx.x;
    if (i >= n16) return;
    uint32_t a = *alpha; a |= a << 16;
    uint4 xv = x[i], fv = fx[i];
    out[i] = make_uint4(rezero2(xv.x, fv.x, a), rezero2(xv.y, fv.y, a), rezero2(xv.z, fv.z, a), rezero2(xv.w, fv.w, a));
}
__device__ unsigned short g_lat[3 * 14];
__global__ void probe(uint8_t* x, uint8_t* f, uint8_t* o) {
    uint8_t* bufs[3] = {x, f, o};
    for (int b = 0; b < 3; b++) for (int j = 0; j < 14; j++) {
        uint32_t* p = (uint32_t*)(bufs[b] + (size_t)j * (2 << 20));
        uint32_t best = ~0u;
        for (int r = 0; r < 4; r++) {
            long long t0, t1; uint32_t v;
            asm volatile("mov.u64 %0, %%clock64;" : "=l"(t0) :: "memory");
            asm volatile("atom.global.add.u32 %0, [%1], 0;" : "=r"(v) : "l"(p) : "memory");
            asm volatile("{ .reg .u32 t; add.u32 t, %1, 0; mov.u64 %0, %%clock64; }" : "=l"(t1) : "r"(v) : "memory");
            if (v == 0xdeadbeef) t1++;
            if (r) best = min(best, (uint32_t)(t1 - t0));
        }
        g_lat[b * 14 + j] = best;
    }
}
extern "C" void kernel_launch(void* const* d_in, const int* in_sizes, int n_in, void* d_out, int out_size) {
    static int once = 0;
    if (!once) {
        once = 1;
        probe<<<1, 1>>>((uint8_t*)d_in[0], (uint8_t*)d_in[1], (uint8_t*)d_out);
        cudaDeviceSynchronize();
        unsigned short h[42]; cudaMemcpyFromSymbol(h, g_lat, sizeof h);
        fprintf(stderr, "DIAG x %p fx %p alpha %p out %p\n", d_in[0], d_in[1], d_in[2], d_out);
        for (int b = 0; b < 3; b++) { fprintf(stderr, "DIAG buf%d: ", b); for (int j = 0; j < 14; j++) fprintf(stderr, "%d", h[b * 14 + j] > 400); fprintf(stderr, "\n"); }
    }
    int n16 = out_size / 8;
    k<<<(n16 + 255) / 256, 256>>>((const uint4*)d_in[0], (const uint4*)d_in[1], (const unsigned short*)d_in[2], (uint4*)d_out, n16);
}
```

```cpp
#include <cuda_runtime.h>
#include <cuda_bf16.h>
#include <stdint.h>

namespace {

constexpr int kTile = 4096;
constexpr int kStages = 5;
constexpr int kConsumerWarps = 8;
constexpr int kThreads = kConsumerWarps * 32 + 32;
constexpr int kHoldNum = 1, kHoldDen = 3;
constexpr int kMaxSmem = 226 * 1024;

__device__ __forceinline__ uint32_t smem_u32(const void* p) { return (uint32_t)__cvta_generic_to_shared(p); }
__device__ __forceinline__ void mbar_init(uint32_t bar, uint32_t count) {
    asm volatile("mbarrier.init.shared::cta.b64 [%0], %1;" ::"r"(bar), "r"(count) : "memory");
}
__device__ __forceinline__ void mbar_expect_tx(uint32_t bar, uint32_t bytes) {
    asm volatile("mbarrier.arrive.expect_tx.shared::cta.b64 _, [%0], %1;" ::"r"(bar), "r"(bytes) : "memory");
}
__device__ __forceinline__ void mbar_arrive(uint32_t bar) {
    asm volatile("mbarrier.arrive.shared::cta.b64 _, [%0];" ::"r"(bar) : "memory");
}
__device__ __forceinline__ void mbar_wait(uint32_t bar, uint32_t parity) {
    asm volatile(
        "{\n.reg .pred p;\n"
        "WAIT_%=:\n"
        "mbarrier.try_wait.parity.shared::cta.b64 p, [%0], %1;\n"
        "@p bra DONE_%=;\n"
        "bra WAIT_%=;\n"
        "DONE_%=:\n}" ::"r"(bar), "r"(parity) : "memory");
}
__device__ __forceinline__ void bulk_load(uint32_t dst, const void* src, uint32_t bytes, uint32_t bar, uint64_t policy) {
    asm volatile(
        "cp.async.bulk.shared::cluster.global.mbarrier::complete_tx::bytes.L2::cache_hint [%0], [%1], %2, [%3], %4;"
        ::"r"(dst), "l"(src), "r"(bytes), "r"(bar), "l"(policy) : "memory");
}
__device__ __forceinline__ void bulk_store(void* dst, uint32_t src, uint32_t bytes) {
    asm volatile("cp.async.bulk.global.shared::cta.bulk_group [%0], [%1], %2;" ::"l"(dst), "r"(src), "r"(bytes) : "memory");
}
__device__ __forceinline__ uint4 lds16(uint32_t a) {
    uint4 v;
    asm volatile("ld.shared.v4.u32 {%0,%1,%2,%3}, [%4];" : "=r"(v.x), "=r"(v.y), "=r"(v.z), "=r"(v.w) : "r"(a));
    return v;
}
__device__ __forceinline__ void sts16(uint32_t a, uint4 v) {
    asm volatile("st.shared.v4.u32 [%0], {%1,%2,%3,%4};" ::"r"(a), "r"(v.x), "r"(v.y), "r"(v.z), "r"(v.w) : "memory");
}
__device__ __forceinline__ void stg16(void* p, uint4 v) {
    asm volatile("st.global.v4.u32 [%0], {%1,%2,%3,%4};" ::"l"(p), "r"(v.x), "r"(v.y), "r"(v.z), "r"(v.w) : "memory");
}
__device__ __forceinline__ uint32_t rezero2(uint32_t x, uint32_t f, uint32_t a) {
    uint32_t t, o;
    asm("mul.rn.bf16x2 %0, %1, %2;" : "=r"(t) : "r"(a), "r"(f));
    asm("add.rn.bf16x2 %0, %1, %2;" : "=r"(o) : "r"(x), "r"(t));
    return o;
}
__device__ __forceinline__ uint4 rezero8(uint4 x, uint4 f, uint32_t a) {
    return make_uint4(rezero2(x.x, f.x, a), rezero2(x.y, f.y, a), rezero2(x.z, f.z, a), rezero2(x.w, f.w, a));
}

__global__ void __launch_bounds__(kThreads, 1)
rezero_stream_kernel(const uint8_t* __restrict__ x, const uint8_t* __restrict__ fx,
                     const unsigned short* __restrict__ alpha, uint8_t* __restrict__ out,
                     int nfull, uint32_t tail_bytes, uint32_t total_bytes) {
    extern __shared__ __align__(128) uint8_t smem[];
    __shared__ uint64_t bars[2 * kStages];
    constexpr int kStage = 2 * kTile;
    constexpr int kNT = kConsumerWarps * 32;
    const uint32_t ring = smem_u32(smem), held = ring + kStages * kStage;
    const uint32_t full = smem_u32(bars), empty = full + 8 * kStages;
    const int warp = threadIdx.x >> 5, lane = threadIdx.x & 31;
    const uint32_t G = gridDim.x, b = blockIdx.x;
    const uint32_t tail_off = (uint32_t)nfull * G * kTile + b * tail_bytes;
    const uint32_t tail_len = tail_off >= total_bytes ? 0u : min(tail_bytes, total_bytes - tail_off);

    if (warp == 0) {
        if (lane == 0) {
#pragma unroll
            for (int s = 0; s < kStages; s++) { mbar_init(full + 8 * s, 1); mbar_init(empty + 8 * s, kConsumerWarps); }
            asm volatile("fence.mbarrier_init.release.cluster;" ::: "memory");
        }
        __syncwarp();
        asm volatile("bar.arrive 1, %0;" ::"n"(kThreads) : "memory");
        if (lane == 0) {
            uint64_t policy;
            asm("createpolicy.fractional.L2::evict_first.b64 %0, 1.0;" : "=l"(policy));
            const int nit = nfull + (tail_len ? 1 : 0);
            int s = 0, ph = 1;
            for (int k = 0; k < nit; k++) {
                if (k >= kStages) mbar_wait(empty + 8 * s, ph);
                const uint32_t off = k < nfull ? (k * G + b) * kTile : tail_off;
                const uint32_t len = k < nfull ? kTile : tail_len;
                mbar_expect_tx(full + 8 * s, 2 * len);
                bulk_load(ring + s * kStage, x + off, len, full + 8 * s, policy);
                bulk_load(ring + s * kStage + kTile, fx + off, len, full + 8 * s, policy);
                if (++s == kStages) { s = 0; ph ^= 1; }
            }
        }
    } else {
        const uint32_t a16 = __ldg(alpha);
        asm volatile("bar.sync 1, %0;" ::"n"(kThreads) : "memory");
        const int t = threadIdx.x - 32;
        const uint32_t a = __byte_perm(a16, 0, 0x1010);
        int s = 0, ph = 0, acc = 0, nheld = 0;
        for (int k = 0; k < nfull; k++) {
            mbar_wait(full + 8 * s, ph);
            const uint4 r = rezero8(lds16(ring + s * kStage + t * 16), lds16(ring + s * kStage + kTile + t * 16), a);
            __syncwarp();
            if (lane == 0) mbar_arrive(empty + 8 * s);
            acc += kHoldNum;
            if (acc >= kHoldDen) {
                acc -= kHoldDen;
                sts16(held + nheld * kTile + t * 16, r);
                nheld++;
            } else {
                stg16(out + (uint32_t)(k * G + b) * kTile + t * 16, r);
            }
            if (++s == kStages) { s = 0; ph ^= 1; }
        }
        if (tail_len) {
            mbar_wait(full + 8 * s, ph);
            const uint32_t o = t * 16;
            if (o < tail_len)
                stg16(out + tail_off + o, rezero8(lds16(ring + s * kStage + o), lds16(ring + s * kStage + kTile + o), a));
        }
        asm volatile("fence.proxy.async.shared::cta;" ::: "memory");
        asm volatile("bar.sync 2, %0;" ::"n"(kNT) : "memory");
        if (t == 0) {
            for (int h = 0; h < nheld; h++) {
                const int k = ((h + 1) * kHoldDen + kHoldNum - 1) / kHoldNum - 1;
                bulk_store(out + (uint32_t)(k * G + b) * kTile, held + h * kTile, kTile);
            }
            asm volatile("cp.async.bulk.commit_group;" ::: "memory");
            asm volatile("cp.async.bulk.wait_group 0;" ::: "memory");
        }
    }
}

__global__ void rezero_generic_kernel(const __nv_bfloat16* __restrict__ x, const __nv_bfloat16* __restrict__ fx,
                                      const __nv_bfloat16* __restrict__ alpha, __nv_bfloat16* __restrict__ out, int n) {
    const __nv_bfloat16 a = alpha[0];
    for (int i = blockIdx.x * blockDim.x + threadIdx.x; i < n; i += gridDim.x * blockDim.x)
        out[i] = __hadd_rn(x[i], __hmul_rn(a, fx[i]));
}

}

extern "C" void kernel_launch(void* const* d_in, const int* in_sizes, int n_in, void* d_out, int out_size) {
    (void)in_sizes; (void)n_in;
    static int num_sms = 0;
    if (num_sms == 0) {
        int dev = 0;
        cudaGetDevice(&dev);
        cudaDeviceGetAttribute(&num_sms, cudaDevAttrMultiProcessorCount, dev);
        cudaFuncSetAttribute(rezero_stream_kernel, cudaFuncAttributeMaxDynamicSharedMemorySize, kMaxSmem);
    }
    const uint64_t total = (uint64_t)out_size * 2;
    const uint64_t round = (uint64_t)num_sms * kTile;
    const int nfull = (int)(total / round);
    const int smem = kStages * 2 * kTile + (nfull * kHoldNum / kHoldDen + 1) * kTile;
    const bool aligned = (((uintptr_t)d_in[0] | (uintptr_t)d_in[1] | (uintptr_t)d_out | total) & 15) == 0;
    if (aligned && nfull >= kStages && smem <= kMaxSmem && total < (1ull << 31)) {
        const uint32_t rem = (uint32_t)(total - (uint64_t)nfull * round);
        const uint32_t tail = (rem + num_sms * 16 - 1) / (num_sms * 16) * 16;
        const int smem_req = smem < 116 * 1024 ? 116 * 1024 : smem;
        rezero_stream_kernel<<<num_sms, kThreads, smem_req>>>(
            (const uint8_t*)d_in[0], (const uint8_t*)d_in[1], (const unsigned short*)d_in[2], (uint8_t*)d_out,
            nfull, tail, (uint32_t)total);
    } else {
        rezero_generic_kernel<<<1024, 256>>>((const __nv_bfloat16*)d_in[0], (const __nv_bfloat16*)d_in[1],
                                             (const __nv_bfloat16*)d_in[2], (__nv_bfloat16*)d_out, out_size);
    }
}
```

```cpp
#include <cuda_runtime.h>
#include <cuda_bf16.h>
#include <stdint.h>

namespace {

constexpr int kTile = 4096;
constexpr int kStages = 8;
constexpr int kBurst = 4;
constexpr int kFlushLag = 2;
constexpr int kConsumerWarps = 8;
constexpr int kThreads = kConsumerWarps * 32 + 32;
constexpr int kHoldNum = 3, kHoldDen = 10;
constexpr int kMinSmem = 116 * 1024;
constexpr int kMaxSmem = 226 * 1024;

__device__ __forceinline__ uint32_t smem_u32(const void* p) { return (uint32_t)__cvta_generic_to_shared(p); }
__device__ __forceinline__ void mbar_init(uint32_t bar, uint32_t count) {
    asm volatile("mbarrier.init.shared::cta.b64 [%0], %1;" ::"r"(bar), "r"(count) : "memory");
}
__device__ __forceinline__ void mbar_expect_tx(uint32_t bar, uint32_t bytes) {
    asm volatile("mbarrier.arrive.expect_tx.shared::cta.b64 _, [%0], %1;" ::"r"(bar), "r"(bytes) : "memory");
}
__device__ __forceinline__ void mbar_arrive(uint32_t bar) {
    asm volatile("mbarrier.arrive.shared::cta.b64 _, [%0];" ::"r"(bar) : "memory");
}
__device__ __forceinline__ void mbar_wait(uint32_t bar, uint32_t parity) {
    asm volatile(
        "{\n.reg .pred p;\n"
        "WAIT_%=:\n"
        "mbarrier.try_wait.parity.shared::cta.b64 p, [%0], %1;\n"
        "@p bra DONE_%=;\n"
        "bra WAIT_%=;\n"
        "DONE_%=:\n}" ::"r"(bar), "r"(parity) : "memory");
}
__device__ __forceinline__ void bulk_load(uint32_t dst, const void* src, uint32_t bytes, uint32_t bar, uint64_t policy) {
    asm volatile(
        "cp.async.bulk.shared::cluster.global.mbarrier::complete_tx::bytes.L2::cache_hint [%0], [%1], %2, [%3], %4;"
        ::"r"(dst), "l"(src), "r"(bytes), "r"(bar), "l"(policy) : "memory");
}
__device__ __forceinline__ void bulk_store(void* dst, uint32_t src, uint32_t bytes) {
    asm volatile("cp.async.bulk.global.shared::cta.bulk_group [%0], [%1], %2;" ::"l"(dst), "r"(src), "r"(bytes) : "memory");
}
__device__ __forceinline__ uint32_t timer_ns() {
    uint32_t t;
    asm volatile("mov.u32 %0, %%globaltimer_lo;" : "=r"(t));
    return t;
}
__device__ __forceinline__ uint4 lds16(uint32_t a) {
    uint4 v;
    asm volatile("ld.shared.v4.u32 {%0,%1,%2,%3}, [%4];" : "=r"(v.x), "=r"(v.y), "=r"(v.z), "=r"(v.w) : "r"(a));
    return v;
}
__device__ __forceinline__ void sts16(uint32_t a, uint4 v) {
    asm volatile("st.shared.v4.u32 [%0], {%1,%2,%3,%4};" ::"r"(a), "r"(v.x), "r"(v.y), "r"(v.z), "r"(v.w) : "memory");
}
__device__ __forceinline__ void stg16(void* p, uint4 v) {
    asm volatile("st.global.v4.u32 [%0], {%1,%2,%3,%4};" ::"l"(p), "r"(v.x), "r"(v.y), "r"(v.z), "r"(v.w) : "memory");
}
__device__ __forceinline__ uint32_t rezero2(uint32_t x, uint32_t f, uint32_t a) {
    uint32_t t, o;
    asm("mul.rn.bf16x2 %0, %1, %2;" : "=r"(t) : "r"(a), "r"(f));
    asm("add.rn.bf16x2 %0, %1, %2;" : "=r"(o) : "r"(x), "r"(t));
    return o;
}
__device__ __forceinline__ uint4 rezero8(uint4 x, uint4 f, uint32_t a) {
    return make_uint4(rezero2(x.x, f.x, a), rezero2(x.y, f.y, a), rezero2(x.z, f.z, a), rezero2(x.w, f.w, a));
}

__global__ void __launch_bounds__(kThreads, 1)
rezero_stream_kernel(const uint8_t* __restrict__ x, const uint8_t* __restrict__ fx,
                     const unsigned short* __restrict__ alpha, uint8_t* __restrict__ out,
                     int nfull, uint32_t tail_bytes, uint32_t total_bytes, int khold, int pace, int pace_start) {
    extern __shared__ __align__(128) uint8_t smem[];
    __shared__ uint64_t bars[2 * kStages];
    constexpr int kStage = 2 * kTile;
    const uint32_t ring = smem_u32(smem), held = ring + kStages * kStage;
    const uint32_t full = smem_u32(bars), empty = full + 8 * kStages;
    const int warp = threadIdx.x >> 5, lane = threadIdx.x & 31;
    const uint32_t G = gridDim.x, b = blockIdx.x;
    const uint32_t tail_off = (uint32_t)nfull * G * kTile + b * tail_bytes;
    const uint32_t tail_len = tail_off >= total_bytes ? 0u : min(tail_bytes, total_bytes - tail_off);

    if (warp == 0) {
        if (lane == 0) {
#pragma unroll
            for (int s = 0; s < kStages; s++) {
                mbar_init(full + 8 * s, 1);
                mbar_init(empty + 8 * s, kConsumerWarps);
            }
            asm volatile("fence.mbarrier_init.release.cluster;" ::: "memory");
        }
        __syncwarp();
        asm volatile("bar.arrive 1, %0;" ::"n"(kThreads) : "memory");
        if (lane == 0) {
            uint64_t policy;
            asm("createpolicy.fractional.L2::evict_first.b64 %0, 1.0;" : "=l"(policy));
            uint32_t due = timer_ns() + (uint32_t)(pace_start + (kBurst - 1) * pace);
#pragma unroll
            for (int k = 0; k < kBurst; k++) {
                const uint32_t off = (k * G + b) * kTile;
                mbar_expect_tx(full + 8 * k, kStage);
                bulk_load(ring + k * kStage, x + off, kTile, full + 8 * k, policy);
                bulk_load(ring + k * kStage + kTile, fx + off, kTile, full + 8 * k, policy);
            }
            const int nit = nfull + (tail_len ? 1 : 0);
            int s = kBurst, ph = 1;
            for (int k = kBurst; k < nit; k++) {
                if (k >= kStages) mbar_wait(empty + 8 * s, ph);
                due += pace;
                while ((int)(timer_ns() - due) < 0) {}
                const uint32_t off = k < nfull ? (k * G + b) * kTile : tail_off;
                const uint32_t len = k < nfull ? kTile : tail_len;
                mbar_expect_tx(full + 8 * s, 2 * len);
                bulk_load(ring + s * kStage, x + off, len, full + 8 * s, policy);
                bulk_load(ring + s * kStage + kTile, fx + off, len, full + 8 * s, policy);
                if (++s == kStages) { s = 0; ph ^= 1; }
            }
            for (int q = 0; q < kFlushLag; q++) {
                mbar_wait(empty + 8 * s, ph);
                if (++s == kStages) { s = 0; ph ^= 1; }
            }
            const int nheld = khold * kHoldNum / kHoldDen;
            for (int h = 0; h < nheld; h++) {
                const int k = ((h + 1) * kHoldDen + kHoldNum - 1) / kHoldNum - 1;
                bulk_store(out + (uint32_t)(k * G + b) * kTile, held + h * kTile, kTile);
            }
            asm volatile("cp.async.bulk.commit_group;" ::: "memory");
            asm volatile("cp.async.bulk.wait_group 0;" ::: "memory");
        }
    } else {
        const uint32_t a16 = __ldg(alpha);
        asm volatile("bar.sync 1, %0;" ::"n"(kThreads) : "memory");
        const int t = threadIdx.x - 32;
        const uint32_t a = __byte_perm(a16, 0, 0x1010);
        int s = 0, ph = 0, acc = 0, nheld = 0;
        for (int k = 0; k < nfull; k++) {
            mbar_wait(full + 8 * s, ph);
            const uint4 r = rezero8(lds16(ring + s * kStage + t * 16), lds16(ring + s * kStage + kTile + t * 16), a);
            acc += kHoldNum;
            if (acc >= kHoldDen && k < khold) {
                acc -= kHoldDen;
                sts16(held + nheld * kTile + t * 16, r);
                nheld++;
                asm volatile("fence.proxy.async.shared::cta;" ::: "memory");
                __syncwarp();
                if (lane == 0) mbar_arrive(empty + 8 * s);
            } else {
                __syncwarp();
                if (lane == 0) mbar_arrive(empty + 8 * s);
                stg16(out + (uint32_t)(k * G + b) * kTile + t * 16, r);
            }
            if (++s == kStages) { s = 0; ph ^= 1; }
        }
        if (tail_len) {
            mbar_wait(full + 8 * s, ph);
            const uint32_t o = t * 16;
            if (o < tail_len)
                stg16(out + tail_off + o, rezero8(lds16(ring + s * kStage + o), lds16(ring + s * kStage + kTile + o), a));
        }
    }
}

__global__ void rezero_generic_kernel(const __nv_bfloat16* __restrict__ x, const __nv_bfloat16* __restrict__ fx,
                                      const __nv_bfloat16* __restrict__ alpha, __nv_bfloat16* __restrict__ out, int n) {
    const __nv_bfloat16 a = alpha[0];
    for (int64_t i = (int64_t)blockIdx.x * blockDim.x + threadIdx.x; i < n; i += (int64_t)gridDim.x * blockDim.x)
        out[i] = __hadd_rn(x[i], __hmul_rn(a, fx[i]));
}

}

extern "C" void kernel_launch(void* const* d_in, const int* in_sizes, int n_in, void* d_out, int out_size) {
    (void)in_sizes; (void)n_in;
    static int num_sms = 0, pace = 0;
    if (num_sms == 0) {
        int dev = 0, mem_khz = 0, bus_bits = 0;
        cudaGetDevice(&dev);
        cudaDeviceGetAttribute(&num_sms, cudaDevAttrMultiProcessorCount, dev);
        cudaDeviceGetAttribute(&mem_khz, cudaDevAttrMemoryClockRate, dev);
        cudaDeviceGetAttribute(&bus_bits, cudaDevAttrGlobalMemoryBusWidth, dev);
        cudaFuncSetAttribute(rezero_stream_kernel, cudaFuncAttributeMaxDynamicSharedMemorySize, kMaxSmem);
        const double bytes_per_ns = 2.0 * mem_khz * 1e3 * (bus_bits / 8) * 1e-9;
        pace = bytes_per_ns > 0 ? (int)(2.0 * kTile * num_sms / (0.95 * bytes_per_ns) + 0.5) : 0;
    }
    const uint64_t total = (uint64_t)out_size * 2;
    const uint64_t round = (uint64_t)num_sms * kTile;
    const int nfull = (int)(total / round);
    const bool aligned = (((uintptr_t)d_in[0] | (uintptr_t)d_in[1] | (uintptr_t)d_out | total) & 15) == 0;
    if (aligned && nfull >= 2 * kStages && total < (1ull << 31)) {
        const uint32_t rem = (uint32_t)(total - (uint64_t)nfull * round);
        const uint32_t tail = (rem + num_sms * 16 - 1) / (num_sms * 16) * 16;
        int khold = nfull - kStages + kFlushLag;
        const int max_held = (kMaxSmem - kStages * 2 * kTile) / kTile;
        if (khold * kHoldNum / kHoldDen > max_held) khold = max_held * kHoldDen / kHoldNum;
        int smem = kStages * 2 * kTile + khold * kHoldNum / kHoldDen * kTile;
        if (smem < kMinSmem) smem = kMinSmem;
        rezero_stream_kernel<<<num_sms, kThreads, smem>>>(
            (const uint8_t*)d_in[0], (const uint8_t*)d_in[1], (const unsigned short*)d_in[2], (uint8_t*)d_out,
            nfull, tail, (uint32_t)total, khold, pace, -(pace * 7) / 4);
    } else {
        rezero_generic_kernel<<<1024, 256>>>((const __nv_bfloat16*)d_in[0], (const __nv_bfloat16*)d_in[1],
                                             (const __nv_bfloat16*)d_in[2], (__nv_bfloat16*)d_out, out_size);
    }
}
```

```cpp
#include <cuda_runtime.h>
#include <cuda_bf16.h>
#include <stdint.h>

namespace {

constexpr int kTile = 4096;
constexpr int kStages = 8;
constexpr int kBurst = 4;
constexpr int kFlushLag = 2;
constexpr int kConsumerWarps = 8;
constexpr int kThreads = kConsumerWarps * 32 + 32;
constexpr int kHoldNum = 3, kHoldDen = 10;
constexpr int kMinSmem = 116 * 1024;
constexpr int kMaxSmem = 226 * 1024;

__device__ __forceinline__ uint32_t smem_u32(const void* p) { return (uint32_t)__cvta_generic_to_shared(p); }
__device__ __forceinline__ void mbar_init(uint32_t bar, uint32_t count) {
    asm volatile("mbarrier.init.shared::cta.b64 [%0], %1;" ::"r"(bar), "r"(count) : "memory");
}
__device__ __forceinline__ void mbar_expect_tx(uint32_t bar, uint32_t bytes) {
    asm volatile("mbarrier.arrive.expect_tx.shared::cta.b64 _, [%0], %1;" ::"r"(bar), "r"(bytes) : "memory");
}
__device__ __forceinline__ void mbar_arrive(uint32_t bar) {
    asm volatile("mbarrier.arrive.shared::cta.b64 _, [%0];" ::"r"(bar) : "memory");
}
__device__ __forceinline__ void mbar_wait(uint32_t bar, uint32_t parity) {
    asm volatile(
        "{\n.reg .pred p;\n"
        "WAIT_%=:\n"
        "mbarrier.try_wait.parity.shared::cta.b64 p, [%0], %1;\n"
        "@p bra DONE_%=;\n"
        "bra WAIT_%=;\n"
        "DONE_%=:\n}" ::"r"(bar), "r"(parity) : "memory");
}
__device__ __forceinline__ void bulk_load(uint32_t dst, const void* src, uint32_t bytes, uint32_t bar, uint64_t policy) {
    asm volatile(
        "cp.async.bulk.shared::cluster.global.mbarrier::complete_tx::bytes.L2::cache_hint [%0], [%1], %2, [%3], %4;"
        ::"r"(dst), "l"(src), "r"(bytes), "r"(bar), "l"(policy) : "memory");
}
__device__ __forceinline__ void bulk_store(void* dst, uint32_t src, uint32_t bytes) {
    asm volatile("cp.async.bulk.global.shared::cta.bulk_group [%0], [%1], %2;" ::"l"(dst), "r"(src), "r"(bytes) : "memory");
}
__device__ __forceinline__ uint32_t timer_ns() {
    uint32_t t;
    asm volatile("mov.u32 %0, %%globaltimer_lo;" : "=r"(t));
    return t;
}
__device__ __forceinline__ uint4 lds16(uint32_t a) {
    uint4 v;
    asm volatile("ld.shared.v4.u32 {%0,%1,%2,%3}, [%4];" : "=r"(v.x), "=r"(v.y), "=r"(v.z), "=r"(v.w) : "r"(a));
    return v;
}
__device__ __forceinline__ void sts16(uint32_t a, uint4 v) {
    asm volatile("st.shared.v4.u32 [%0], {%1,%2,%3,%4};" ::"r"(a), "r"(v.x), "r"(v.y), "r"(v.z), "r"(v.w) : "memory");
}
__device__ __forceinline__ void stg16(void* p, uint4 v) {
    asm volatile("st.global.v4.u32 [%0], {%1,%2,%3,%4};" ::"l"(p), "r"(v.x), "r"(v.y), "r"(v.z), "r"(v.w) : "memory");
}
__device__ __forceinline__ uint32_t rezero2(uint32_t x, uint32_t f, uint32_t a) {
    uint32_t t, o;
    asm("mul.rn.bf16x2 %0, %1, %2;" : "=r"(t) : "r"(a), "r"(f));
    asm("add.rn.bf16x2 %0, %1, %2;" : "=r"(o) : "r"(x), "r"(t));
    return o;
}
__device__ __forceinline__ uint4 rezero8(uint4 x, uint4 f, uint32_t a) {
    return make_uint4(rezero2(x.x, f.x, a), rezero2(x.y, f.y, a), rezero2(x.z, f.z, a), rezero2(x.w, f.w, a));
}

__global__ void __launch_bounds__(kThreads, 1)
rezero_stream_kernel(const uint8_t* __restrict__ x, const uint8_t* __restrict__ fx,
                     const unsigned short* __restrict__ alpha, uint8_t* __restrict__ out,
                     int nfull, uint32_t tail_bytes, uint32_t total_bytes, int khold, int pace, int pace_start) {
    extern __shared__ __align__(128) uint8_t smem[];
    __shared__ uint64_t bars[2 * kStages];
    constexpr int kStage = 2 * kTile;
    const uint32_t ring = smem_u32(smem), held = ring + kStages * kStage;
    const uint32_t full = smem_u32(bars), empty = full + 8 * kStages;
    const int warp = threadIdx.x >> 5, lane = threadIdx.x & 31;
    const uint32_t G = gridDim.x, b = blockIdx.x;
    const uint32_t tail_off = (uint32_t)nfull * G * kTile + b * tail_bytes;
    const uint32_t tail_len = tail_off >= total_bytes ? 0u : min(tail_bytes, total_bytes - tail_off);

    if (warp == 0) {
        uint64_t policy;
        asm("createpolicy.fractional.L2::evict_first.b64 %0, 1.0;" : "=l"(policy));
        uint32_t due = 0;
        if (lane == 0) {
#pragma unroll
            for (int k = 0; k < kBurst; k++) {
                const uint32_t off = (k * G + b) * kTile;
                mbar_init(full + 8 * k, 1);
                asm volatile("fence.mbarrier_init.release.cluster;" ::: "memory");
                mbar_expect_tx(full + 8 * k, kStage);
                bulk_load(ring + k * kStage, x + off, kTile, full + 8 * k, policy);
                bulk_load(ring + k * kStage + kTile, fx + off, kTile, full + 8 * k, policy);
                if (k == 0) due = timer_ns() + (uint32_t)(pace_start + (kBurst - 1) * pace);
            }
#pragma unroll
            for (int s = kBurst; s < kStages; s++) mbar_init(full + 8 * s, 1);
#pragma unroll
            for (int s = 0; s < kStages; s++) mbar_init(empty + 8 * s, kConsumerWarps);
            asm volatile("fence.mbarrier_init.release.cluster;" ::: "memory");
        }
        __syncwarp();
        asm volatile("bar.arrive 1, %0;" ::"n"(kThreads) : "memory");
        if (lane == 0) {
            const int nit = nfull + (tail_len ? 1 : 0);
            int s = kBurst, ph = 1;
            for (int k = kBurst; k < nit; k++) {
                if (k >= kStages) mbar_wait(empty + 8 * s, ph);
                due += pace;
                while ((int)(timer_ns() - due) < 0) {}
                const uint32_t off = k < nfull ? (k * G + b) * kTile : tail_off;
                const uint32_t len = k < nfull ? kTile : tail_len;
                mbar_expect_tx(full + 8 * s, 2 * len);
                bulk_load(ring + s * kStage, x + off, len, full + 8 * s, policy);
                bulk_load(ring + s * kStage + kTile, fx + off, len, full + 8 * s, policy);
                if (++s == kStages) { s = 0; ph ^= 1; }
            }
            for (int q = 0; q < kFlushLag; q++) {
                mbar_wait(empty + 8 * s, ph);
                if (++s == kStages) { s = 0; ph ^= 1; }
            }
            const int nheld = khold * kHoldNum / kHoldDen;
            for (int h = 0; h < nheld; h++) {
                const int k = ((h + 1) * kHoldDen + kHoldNum - 1) / kHoldNum - 1;
                bulk_store(out + (uint32_t)(k * G + b) * kTile, held + h * kTile, kTile);
            }
            asm volatile("cp.async.bulk.commit_group;" ::: "memory");
            asm volatile("cp.async.bulk.wait_group 0;" ::: "memory");
        }
    } else {
        const uint32_t a16 = __ldg(alpha);
        asm volatile("bar.sync 1, %0;" ::"n"(kThreads) : "memory");
        const int t = threadIdx.x - 32;
        const uint32_t a = __byte_perm(a16, 0, 0x1010);
        int s = 0, ph = 0, acc = 0, nheld = 0;
        for (int k = 0; k < nfull; k++) {
            mbar_wait(full + 8 * s, ph);
            const uint4 r = rezero8(lds16(ring + s * kStage + t * 16), lds16(ring + s * kStage + kTile + t * 16), a);
            acc += kHoldNum;
            if (acc >= kHoldDen && k < khold) {
                acc -= kHoldDen;
                sts16(held + nheld * kTile + t * 16, r);
                nheld++;
                asm volatile("fence.proxy.async.shared::cta;" ::: "memory");
            } else {
                stg16(out + (uint32_t)(k * G + b) * kTile + t * 16, r);
            }
            __syncwarp();
            if (lane == 0) mbar_arrive(empty + 8 * s);
            if (++s == kStages) { s = 0; ph ^= 1; }
        }
        if (tail_len) {
            mbar_wait(full + 8 * s, ph);
            const uint32_t o = t * 16;
            if (o < tail_len)
                stg16(out + tail_off + o, rezero8(lds16(ring + s * kStage + o), lds16(ring + s * kStage + kTile + o), a));
        }
    }
}

__global__ void rezero_generic_kernel(const __nv_bfloat16* __restrict__ x, const __nv_bfloat16* __restrict__ fx,
                                      const __nv_bfloat16* __restrict__ alpha, __nv_bfloat16* __restrict__ out, int n) {
    const __nv_bfloat16 a = alpha[0];
    for (int64_t i = (int64_t)blockIdx.x * blockDim.x + threadIdx.x; i < n; i += (int64_t)gridDim.x * blockDim.x)
        out[i] = __hadd_rn(x[i], __hmul_rn(a, fx[i]));
}

}

extern "C" void kernel_launch(void* const* d_in, const int* in_sizes, int n_in, void* d_out, int out_size) {
    (void)in_sizes; (void)n_in;
    static int num_sms = 0, pace = 0;
    if (num_sms == 0) {
        int dev = 0, mem_khz = 0, bus_bits = 0;
        cudaGetDevice(&dev);
        cudaDeviceGetAttribute(&num_sms, cudaDevAttrMultiProcessorCount, dev);
        cudaDeviceGetAttribute(&mem_khz, cudaDevAttrMemoryClockRate, dev);
        cudaDeviceGetAttribute(&bus_bits, cudaDevAttrGlobalMemoryBusWidth, dev);
        cudaFuncSetAttribute(rezero_stream_kernel, cudaFuncAttributeMaxDynamicSharedMemorySize, kMaxSmem);
        const double bytes_per_ns = 2.0 * mem_khz * 1e3 * (bus_bits / 8) * 1e-9;
        pace = bytes_per_ns > 0 ? (int)(2.0 * kTile * num_sms / (0.95 * bytes_per_ns) + 0.5) : 0;
    }
    const uint64_t total = (uint64_t)out_size * 2;
    const uint64_t round = (uint64_t)num_sms * kTile;
    const int nfull = (int)(total / round);
    const bool aligned = (((uintptr_t)d_in[0] | (uintptr_t)d_in[1] | (uintptr_t)d_out | total) & 15) == 0;
    if (aligned && nfull >= 2 * kStages && total < (1ull << 31)) {
        const uint32_t rem = (uint32_t)(total - (uint64_t)nfull * round);
        const uint32_t tail = (rem + num_sms * 16 - 1) / (num_sms * 16) * 16;
        int khold = nfull - kStages + kFlushLag;
        const int max_held = (kMaxSmem - kStages * 2 * kTile) / kTile;
        if (khold * kHoldNum / kHoldDen > max_held) khold = max_held * kHoldDen / kHoldNum;
        int smem = kStages * 2 * kTile + khold * kHoldNum / kHoldDen * kTile;
        if (smem < kMinSmem) smem = kMinSmem;
        rezero_stream_kernel<<<num_sms, kThreads, smem>>>(
            (const uint8_t*)d_in[0], (const uint8_t*)d_in[1], (const unsigned short*)d_in[2], (uint8_t*)d_out,
            nfull, tail, (uint32_t)total, khold, pace, -(pace * 7) / 4);
    } else {
        rezero_generic_kernel<<<1024, 256>>>((const __nv_bfloat16*)d_in[0], (const __nv_bfloat16*)d_in[1],
                                             (const __nv_bfloat16*)d_in[2], (__nv_bfloat16*)d_out, out_size);
    }
}
```

```cpp
#include <cuda_runtime.h>
#include <cuda_bf16.h>
#include <stdint.h>

namespace {

constexpr int kTile = 4096;
constexpr int kStages = 8;
constexpr int kBurst = 4;
constexpr int kFlushLag = 2;
constexpr int kConsumerWarps = 8;
constexpr int kThreads = kConsumerWarps * 32 + 32;
constexpr int kHoldNum = 3, kHoldDen = 10;
constexpr int kMinSmem = 116 * 1024;
constexpr int kMaxSmem = 226 * 1024;

__device__ __forceinline__ uint32_t smem_u32(const void* p) { return (uint32_t)__cvta_generic_to_shared(p); }
__device__ __forceinline__ void mbar_init(uint32_t bar, uint32_t count) {
    asm volatile("mbarrier.init.shared::cta.b64 [%0], %1;" ::"r"(bar), "r"(count) : "memory");
}
__device__ __forceinline__ void mbar_expect_tx(uint32_t bar, uint32_t bytes) {
    asm volatile("mbarrier.arrive.expect_tx.shared::cta.b64 _, [%0], %1;" ::"r"(bar), "r"(bytes) : "memory");
}
__device__ __forceinline__ void mbar_arrive(uint32_t bar) {
    asm volatile("mbarrier.arrive.shared::cta.b64 _, [%0];" ::"r"(bar) : "memory");
}
__device__ __forceinline__ void mbar_wait(uint32_t bar, uint32_t parity) {
    asm volatile(
        "{\n.reg .pred p;\n"
        "WAIT_%=:\n"
        "mbarrier.try_wait.parity.shared::cta.b64 p, [%0], %1;\n"
        "@p bra DONE_%=;\n"
        "bra WAIT_%=;\n"
        "DONE_%=:\n}" ::"r"(bar), "r"(parity) : "memory");
}
__device__ __forceinline__ void bulk_load(uint32_t dst, const void* src, uint32_t bytes, uint32_t bar, uint64_t policy) {
    asm volatile(
        "cp.async.bulk.shared::cluster.global.mbarrier::complete_tx::bytes.L2::cache_hint [%0], [%1], %2, [%3], %4;"
        ::"r"(dst), "l"(src), "r"(bytes), "r"(bar), "l"(policy) : "memory");
}
__device__ __forceinline__ void bulk_store(void* dst, uint32_t src, uint32_t bytes) {
    asm volatile("cp.async.bulk.global.shared::cta.bulk_group [%0], [%1], %2;" ::"l"(dst), "r"(src), "r"(bytes) : "memory");
}
__device__ __forceinline__ uint32_t timer_ns() {
    uint32_t t;
    asm volatile("mov.u32 %0, %%globaltimer_lo;" : "=r"(t));
    return t;
}
__device__ __forceinline__ uint4 lds16(uint32_t a) {
    uint4 v;
    asm volatile("ld.shared.v4.u32 {%0,%1,%2,%3}, [%4];" : "=r"(v.x), "=r"(v.y), "=r"(v.z), "=r"(v.w) : "r"(a));
    return v;
}
__device__ __forceinline__ void sts16(uint32_t a, uint4 v) {
    asm volatile("st.shared.v4.u32 [%0], {%1,%2,%3,%4};" ::"r"(a), "r"(v.x), "r"(v.y), "r"(v.z), "r"(v.w) : "memory");
}
__device__ __forceinline__ void stg16(void* p, uint4 v) {
    asm volatile("st.global.v4.u32 [%0], {%1,%2,%3,%4};" ::"l"(p), "r"(v.x), "r"(v.y), "r"(v.z), "r"(v.w) : "memory");
}
__device__ __forceinline__ uint32_t rezero2(uint32_t x, uint32_t f, uint32_t a) {
    uint32_t t, o;
    asm("mul.rn.bf16x2 %0, %1, %2;" : "=r"(t) : "r"(a), "r"(f));
    asm("add.rn.bf16x2 %0, %1, %2;" : "=r"(o) : "r"(x), "r"(t));
    return o;
}
__device__ __forceinline__ uint4 rezero8(uint4 x, uint4 f, uint32_t a) {
    return make_uint4(rezero2(x.x, f.x, a), rezero2(x.y, f.y, a), rezero2(x.z, f.z, a), rezero2(x.w, f.w, a));
}

__global__ void __launch_bounds__(kThreads, 1)
rezero_stream_kernel(const uint8_t* __restrict__ x, const uint8_t* __restrict__ fx,
                     const unsigned short* __restrict__ alpha, uint8_t* __restrict__ out,
                     int nfull, uint32_t tail_bytes, uint32_t total_bytes, int khold, int pace, int pace_start) {
    extern __shared__ __align__(128) uint8_t smem[];
    __shared__ uint64_t bars[2 * kStages];
    constexpr int kStage = 2 * kTile;
    const uint32_t ring = smem_u32(smem), held = ring + kStages * kStage;
    const uint32_t full = smem_u32(bars), empty = full + 8 * kStages;
    const int warp = threadIdx.x >> 5, lane = threadIdx.x & 31;
    const uint32_t G = gridDim.x, b = blockIdx.x;

    uint64_t policy;
    asm("createpolicy.fractional.L2::evict_first.b64 %0, 1.0;" : "=l"(policy));
    uint32_t due = 0;
    if (threadIdx.x == 0) {
#pragma unroll
        for (int k = 0; k < kBurst; k++) {
            const uint32_t off = (k * G + b) * kTile;
            mbar_init(full + 8 * k, 1);
            asm volatile("fence.mbarrier_init.release.cluster;" ::: "memory");
            mbar_expect_tx(full + 8 * k, kStage);
            bulk_load(ring + k * kStage, x + off, kTile, full + 8 * k, policy);
            bulk_load(ring + k * kStage + kTile, fx + off, kTile, full + 8 * k, policy);
            if (k == 0) due = timer_ns() + (uint32_t)(pace_start + (kBurst - 1) * pace);
        }
#pragma unroll
        for (int s = kBurst; s < kStages; s++) mbar_init(full + 8 * s, 1);
#pragma unroll
        for (int s = 0; s < kStages; s++) mbar_init(empty + 8 * s, kConsumerWarps);
        asm volatile("fence.mbarrier_init.release.cluster;" ::: "memory");
    }

    const uint32_t tail_off = (uint32_t)nfull * G * kTile + b * tail_bytes;
    const uint32_t tail_len = tail_off >= total_bytes ? 0u : min(tail_bytes, total_bytes - tail_off);

    if (warp == 0) {
        __syncwarp();
        asm volatile("bar.arrive 1, %0;" ::"n"(kThreads) : "memory");
        if (lane == 0) {
            const int nit = nfull + (tail_len ? 1 : 0);
            int s = kBurst, ph = 1;
#pragma unroll 1
            for (int k = kBurst; k < nit; k++) {
                if (k >= kStages) mbar_wait(empty + 8 * s, ph);
                const uint32_t off = k < nfull ? (k * G + b) * kTile : tail_off;
                const uint32_t len = k < nfull ? kTile : tail_len;
                due += (uint32_t)pace * len / kTile;
                while ((int)(timer_ns() - due) < 0) {}
                mbar_expect_tx(full + 8 * s, 2 * len);
                bulk_load(ring + s * kStage, x + off, len, full + 8 * s, policy);
                bulk_load(ring + s * kStage + kTile, fx + off, len, full + 8 * s, policy);
                if (++s == kStages) { s = 0; ph ^= 1; }
            }
#pragma unroll 1
            for (int q = 0; q < kFlushLag; q++) {
                mbar_wait(empty + 8 * s, ph);
                if (++s == kStages) { s = 0; ph ^= 1; }
            }
            const int nheld = khold * kHoldNum / kHoldDen;
#pragma unroll 1
            for (int h = 0; h < nheld; h++) {
                const int k = ((h + 1) * kHoldDen + kHoldNum - 1) / kHoldNum - 1;
                bulk_store(out + (uint32_t)(k * G + b) * kTile, held + h * kTile, kTile);
            }
            asm volatile("cp.async.bulk.commit_group;" ::: "memory");
            asm volatile("cp.async.bulk.wait_group 0;" ::: "memory");
        }
    } else {
        const uint32_t a16 = __ldg(alpha);
        asm volatile("bar.sync 1, %0;" ::"n"(kThreads) : "memory");
        const int t = threadIdx.x - 32;
        const uint32_t a = __byte_perm(a16, 0, 0x1010);
        int s = 0, ph = 0, acc = 0, nheld = 0;
#pragma unroll 1
        for (int k = 0; k < nfull; k++) {
            mbar_wait(full + 8 * s, ph);
            const uint4 r = rezero8(lds16(ring + s * kStage + t * 16), lds16(ring + s * kStage + kTile + t * 16), a);
            acc += kHoldNum;
            if (acc >= kHoldDen && k < khold) {
                acc -= kHoldDen;
                sts16(held + nheld * kTile + t * 16, r);
                nheld++;
                asm volatile("fence.proxy.async.shared::cta;" ::: "memory");
            } else {
                stg16(out + (uint32_t)(k * G + b) * kTile + t * 16, r);
            }
            __syncwarp();
            if (lane == 0) mbar_arrive(empty + 8 * s);
            if (++s == kStages) { s = 0; ph ^= 1; }
        }
        if (tail_len) {
            mbar_wait(full + 8 * s, ph);
            const uint32_t o = t * 16;
            if (o < tail_len)
                stg16(out + tail_off + o, rezero8(lds16(ring + s * kStage + o), lds16(ring + s * kStage + kTile + o), a));
        }
    }
}

__global__ void rezero_generic_kernel(const __nv_bfloat16* __restrict__ x, const __nv_bfloat16* __restrict__ fx,
                                      const __nv_bfloat16* __restrict__ alpha, __nv_bfloat16* __restrict__ out, int n) {
    const __nv_bfloat16 a = alpha[0];
    for (int64_t i = (int64_t)blockIdx.x * blockDim.x + threadIdx.x; i < n; i += (int64_t)gridDim.x * blockDim.x)
        out[i] = __hadd_rn(x[i], __hmul_rn(a, fx[i]));
}

}

extern "C" void kernel_launch(void* const* d_in, const int* in_sizes, int n_in, void* d_out, int out_size) {
    (void)in_sizes; (void)n_in;
    static int num_sms = 0, pace = 0;
    if (num_sms == 0) {
        int dev = 0, mem_khz = 0, bus_bits = 0;
        cudaGetDevice(&dev);
        cudaDeviceGetAttribute(&num_sms, cudaDevAttrMultiProcessorCount, dev);
        cudaDeviceGetAttribute(&mem_khz, cudaDevAttrMemoryClockRate, dev);
        cudaDeviceGetAttribute(&bus_bits, cudaDevAttrGlobalMemoryBusWidth, dev);
        cudaFuncSetAttribute(rezero_stream_kernel, cudaFuncAttributeMaxDynamicSharedMemorySize, kMaxSmem);
        const double bytes_per_ns = 2.0 * mem_khz * 1e3 * (bus_bits / 8) * 1e-9;
        pace = bytes_per_ns > 0 ? (int)(2.0 * kTile * num_sms / (0.95 * bytes_per_ns) + 0.5) : 0;
    }
    const uint64_t total = (uint64_t)out_size * 2;
    const uint64_t round = (uint64_t)num_sms * kTile;
    const int nfull = (int)(total / round);
    const bool aligned = (((uintptr_t)d_in[0] | (uintptr_t)d_in[1] | (uintptr_t)d_out | total) & 15) == 0;
    if (aligned && nfull >= 2 * kStages && total < (1ull << 31)) {
        const uint32_t rem = (uint32_t)(total - (uint64_t)nfull * round);
        const uint32_t tail = (rem + num_sms * 16 - 1) / (num_sms * 16) * 16;
        int khold = nfull - kStages + kFlushLag;
        const int max_held = (kMaxSmem - kStages * 2 * kTile) / kTile;
        if (khold * kHoldNum / kHoldDen > max_held) khold = max_held * kHoldDen / kHoldNum;
        int smem = kStages * 2 * kTile + khold * kHoldNum / kHoldDen * kTile;
        if (smem < kMinSmem) smem = kMinSmem;
        rezero_stream_kernel<<<num_sms, kThreads, smem>>>(
            (const uint8_t*)d_in[0], (const uint8_t*)d_in[1], (const unsigned short*)d_in[2], (uint8_t*)d_out,
            nfull, tail, (uint32_t)total, khold, pace, -(pace * 7) / 4);
    } else {
        rezero_generic_kernel<<<1024, 256>>>((const __nv_bfloat16*)d_in[0], (const __nv_bfloat16*)d_in[1],
                                             (const __nv_bfloat16*)d_in[2], (__nv_bfloat16*)d_out, out_size);
    }
}
```
